```python
import torch

def _softmax(x, axis=-1):
    return torch.softmax(x, dim=axis)
def _gelu(x):
    return torch.nn.functional.gelu(x, approximate="tanh")
def _silu(x):
    return torch.nn.functional.silu(x)
def _sigmoid(x):
    return torch.sigmoid(x)
def _layernorm(x, axis=-1, eps=1e-5):
    m = x.mean(dim=axis, keepdim=True)
    v = x.var(dim=axis, keepdim=True, unbiased=False)
    return (x - m) / torch.sqrt(v + eps)
def _scatter_add(tgt, idx, src, axis=0):
    return tgt.clone().index_add_(axis, idx, src)
def _segment_sum(src, seg, n):
    out = torch.zeros((n,) + src.shape[1:], dtype=src.dtype)
    return out.index_add_(0, seg, src)
def _pad(x, pw):
    flat = tuple(v for pair in reversed(pw) for v in pair)
    return torch.nn.functional.pad(x, flat)

kernel_name = 'standalone__gqa_block_cached__decode'

def setup_inputs():

    _w = (lambda a: (lambda t: t.to(torch.bfloat16) if t.is_floating_point() else t)(torch.as_tensor(a)))
    B, Sq, D = 8, 1, 512
    Hq, Hkv, Sk, Dh = 32, 8, 8192, 128
    assert Hq % Hkv == 0, (Hq, Hkv)
    return {
        "x": _w((lambda *s: torch.randn(*s, dtype=torch.bfloat16) * 0.8)(B, Sq, D)),
        "k_cache": _w((lambda *s: torch.randn(*s, dtype=torch.bfloat16) * 0.8)(B, Hkv, Sk, Dh)),
        "v_cache": _w((lambda *s: torch.randn(*s, dtype=torch.bfloat16) * 0.05)(B, Hkv, Sk, Dh)),
        "wq": _w((lambda *s: torch.randn(*s, dtype=torch.bfloat16) * 0.8)(D, Hq * Dh) * (D ** -0.5)),
        "wo": _w((lambda *s: torch.randn(*s, dtype=torch.bfloat16) * 0.05)(Hq * Dh, D) * ((Hq * Dh) ** -0.5)),
    }

def reference(x, k_cache, v_cache, wq, wo):
    B, Sq, D = x.shape
    Hq, Dh = 32, 128
    Hkv = k_cache.shape[1]
    rep = Hq // Hkv
    q = (lambda x, *d: x.permute(*d))((x @ wq).reshape(B, Sq, Hq, Dh), 0, 2, 1, 3)
    k = (lambda x, n, axis: torch.repeat_interleave(x, n, dim=axis))(k_cache, rep, axis=1)
    v = (lambda x, n, axis: torch.repeat_interleave(x, n, dim=axis))(v_cache, rep, axis=1)
    scores = torch.einsum("bhqd,bhkd->bhqk", q, k) * (Dh ** -0.5)
    p = _softmax(scores, axis=-1)
    o = torch.einsum("bhqk,bhkd->bhqd", p, v)
    return (lambda x, *d: x.permute(*d))(o, 0, 2, 1, 3).reshape(B, Sq, Hq * Dh) @ wo
```

```cpp
#include <cuda_runtime.h>
#include <cuda_bf16.h>
#include <cuda.h>
#include <stdint.h>

namespace {

constexpr int kB = 8, kHkv = 8, kSk = 8192, kDh = 128, kD = 512, kHqDh = 4096;
constexpr int kSplits = 2;
constexpr int kCTAs = kB * kHkv * kSplits;
constexpr int kKeysPerCta = kSk / kSplits;
constexpr int kTileKeys = 128;
constexpr int kTiles = kKeysPerCta / kTileKeys;
constexpr int kSlotBytes = kTileKeys * kDh * 2;
constexpr int kSlots = 6;
constexpr int kConsumerWarps = 8;
constexpr int kThreads = (kConsumerWarps + 1) * 32;
constexpr int kItems = 2 * kTiles + 2;
constexpr int kColsPerCta = 32;
constexpr unsigned kSpinLimit = 1u << 22;

constexpr int kOffRing = 0;
constexpr int kOffA    = kSlots * kSlotBytes;
constexpr int kOffWO   = kOffA + 8192;
constexpr int kOffML   = kOffWO + 16384;
constexpr int kOffBar  = kOffML + 256;
constexpr int kOffFlag = kOffBar + 2 * kSlots * 8;
constexpr int kSmemBytes = kOffFlag + 16 + 1024;

__device__ __nv_bfloat16 g_q[kB * kHqDh];
__device__ float g_partO[kCTAs][4 * kDh];
__device__ float g_partML[kCTAs][8];
__device__ float g_partY[kHkv][kB][kD];
__device__ unsigned g_qcount[kHkv];
__device__ unsigned g_pcount[kHkv];
__device__ unsigned g_fcount[kD / kColsPerCta];
__device__ unsigned g_done;

__device__ __forceinline__ uint32_t smem_u32(const void* p) { return (uint32_t)__cvta_generic_to_shared(p); }

__device__ __forceinline__ void mbar_init(uint32_t bar, uint32_t cnt) {
    asm volatile("mbarrier.init.shared::cta.b64 [%0], %1;" ::"r"(bar), "r"(cnt) : "memory");
}
__device__ __forceinline__ void mbar_expect_tx(uint32_t bar, uint32_t bytes) {
    asm volatile("mbarrier.arrive.expect_tx.shared::cta.b64 _, [%0], %1;" ::"r"(bar), "r"(bytes) : "memory");
}
__device__ __forceinline__ void mbar_arrive(uint32_t bar) {
    asm volatile("mbarrier.arrive.shared::cta.b64 _, [%0];" ::"r"(bar) : "memory");
}
__device__ __forceinline__ bool mbar_try_wait(uint32_t bar, uint32_t parity) {
    uint32_t ok;
    asm volatile(
        "{\n.reg .pred p;\n"
        "mbarrier.try_wait.parity.shared::cta.b64 p, [%1], %2;\n"
        "selp.u32 %0, 1, 0, p;\n}"
        : "=r"(ok) : "r"(bar), "r"(parity) : "memory");
    return ok != 0;
}
__device__ __forceinline__ void mbar_wait(uint32_t bar, uint32_t parity) {
    for (unsigned it = 0; !mbar_try_wait(bar, parity); ++it) {
        if (it > (1u << 26)) __trap();
    }
}
__device__ __forceinline__ void tma_2d(uint32_t dst, const CUtensorMap* tm, int c0, int c1, uint32_t bar) {
    asm volatile(
        "cp.async.bulk.tensor.2d.shared::cluster.global.mbarrier::complete_tx::bytes [%0], [%1, {%3, %4}], [%2];"
        ::"r"(dst), "l"((uint64_t)tm), "r"(bar), "r"(c0), "r"(c1) : "memory");
}
__device__ __forceinline__ void bulk_1d(uint32_t dst, const void* src, uint32_t bytes, uint32_t bar) {
    asm volatile(
        "cp.async.bulk.shared::cluster.global.mbarrier::complete_tx::bytes [%0], [%1], %2, [%3];"
        ::"r"(dst), "l"(src), "r"(bytes), "r"(bar) : "memory");
}
__device__ __forceinline__ void ldsm_x4(uint32_t (&r)[4], uint32_t addr) {
    asm volatile("ldmatrix.sync.aligned.m8n8.x4.shared.b16 {%0,%1,%2,%3}, [%4];"
                 : "=r"(r[0]), "=r"(r[1]), "=r"(r[2]), "=r"(r[3]) : "r"(addr) : "memory");
}
__device__ __forceinline__ void ldsm_x4_t(uint32_t (&r)[4], uint32_t addr) {
    asm volatile("ldmatrix.sync.aligned.m8n8.x4.trans.shared.b16 {%0,%1,%2,%3}, [%4];"
                 : "=r"(r[0]), "=r"(r[1]), "=r"(r[2]), "=r"(r[3]) : "r"(addr) : "memory");
}
__device__ __forceinline__ void mma_bf16(float (&c)[4], uint32_t a0, uint32_t a1, uint32_t a2, uint32_t a3,
                                         uint32_t b0, uint32_t b1) {
    asm volatile(
        "mma.sync.aligned.m16n8k16.row.col.f32.bf16.bf16.f32 {%0,%1,%2,%3}, {%4,%5,%6,%7}, {%8,%9}, {%0,%1,%2,%3};"
        : "+f"(c[0]), "+f"(c[1]), "+f"(c[2]), "+f"(c[3])
        : "r"(a0), "r"(a1), "r"(a2), "r"(a3), "r"(b0), "r"(b1));
}
__device__ __forceinline__ uint32_t pack_bf16(float lo, float hi) {
    __nv_bfloat162 v = __floats2bfloat162_rn(lo, hi);
    return *reinterpret_cast<uint32_t*>(&v);
}
__device__ __forceinline__ void consumer_bar() { asm volatile("bar.sync 1, 256;" ::: "memory"); }
__device__ __forceinline__ unsigned ld_acquire(const unsigned* p) {
    unsigned v;
    asm volatile("ld.acquire.gpu.global.u32 %0, [%1];" : "=r"(v) : "l"(p) : "memory");
    return v;
}
__device__ __forceinline__ void red_release_add(unsigned* p, unsigned v) {
    asm volatile("red.release.gpu.global.add.u32 [%0], %1;" ::"l"(p), "r"(v) : "memory");
}
__device__ __forceinline__ void spin_until(const unsigned* p, unsigned target) {
    for (unsigned it = 0; it < kSpinLimit; ++it) {
        if (ld_acquire(p) >= target) break;
    }
}

__device__ __forceinline__ void gemv_8x512x32(uint32_t sA, uint32_t sW, float* red, int warp, int lane) {
    float c[2][4] = {{0.f, 0.f, 0.f, 0.f}, {0.f, 0.f, 0.f, 0.f}};
    const int g = lane >> 2, t = lane & 3;
#pragma unroll
    for (int ks = 0; ks < 4; ++ks) {
        const int k0 = warp * 64 + ks * 16;
        uint32_t b0, b1;
        asm volatile("ld.shared.b32 %0, [%1];" : "=r"(b0) : "r"(sA + (g * 512 + k0 + 2 * t) * 2) : "memory");
        asm volatile("ld.shared.b32 %0, [%1];" : "=r"(b1) : "r"(sA + (g * 512 + k0 + 2 * t + 8) * 2) : "memory");
#pragma unroll
        for (int mt = 0; mt < 2; ++mt) {
            uint32_t a[4];
            const int krow = k0 + (lane & 7) + 8 * (lane >> 4);
            const int col = 16 * mt + 8 * ((lane >> 3) & 1);
            ldsm_x4_t(a, sW + krow * 64 + col * 2);
            mma_bf16(c[mt], a[0], a[1], a[2], a[3], b0, b1);
        }
    }
    float4* r4 = reinterpret_cast<float4*>(red + warp * 256);
    r4[lane] = make_float4(c[0][0], c[0][1], c[0][2], c[0][3]);
    r4[32 + lane] = make_float4(c[1][0], c[1][1], c[1][2], c[1][3]);
}
__device__ __forceinline__ float gemv_reduce(const float* red, int j, int& col, int& row) {
    float s = 0.f;
#pragma unroll
    for (int w = 0; w < 8; ++w) s += red[w * 256 + j];
    const int mt = j >> 7, ln = (j & 127) >> 2, cc = j & 3;
    col = 16 * mt + (ln >> 2) + 8 * (cc >> 1);
    row = 2 * (ln & 3) + (cc & 1);
    return s;
}

__global__ void __launch_bounds__(kThreads, 1)
gqa_decode_fused(const __grid_constant__ CUtensorMap tmK, const __grid_constant__ CUtensorMap tmV,
                 const __grid_constant__ CUtensorMap tmWq, const __grid_constant__ CUtensorMap tmWo,
                 const __nv_bfloat16* __restrict__ x, __nv_bfloat16* __restrict__ out) {
    extern __shared__ uint8_t smem_raw[];
    uint8_t* smem = reinterpret_cast<uint8_t*>((reinterpret_cast<uintptr_t>(smem_raw) + 1023) & ~(uintptr_t)1023);
    const uint32_t sbase = smem_u32(smem);
    const uint32_t sRing = sbase + kOffRing;
    const uint32_t sA = sbase + kOffA;
    const uint32_t barFull = sbase + kOffBar;
    const uint32_t barEmpty = barFull + kSlots * 8;
    float* sRed = reinterpret_cast<float*>(smem + kOffWO);
    float* sWO = reinterpret_cast<float*>(smem + kOffWO);
    float* sML = reinterpret_cast<float*>(smem + kOffML);
    volatile unsigned* sFlag = reinterpret_cast<volatile unsigned*>(smem + kOffFlag);

    const int tid = threadIdx.x, warp = tid >> 5, lane = tid & 31;
    const int cta = blockIdx.x;

    if (tid == 0) {
        for (int i = 0; i < kSlots; ++i) {
            mbar_init(barFull + i * 8, 1);
            mbar_init(barEmpty + i * 8, kConsumerWarps);
        }
        asm volatile("fence.mbarrier_init.release.cluster;" ::: "memory");
    }
    __syncthreads();

    if (warp == kConsumerWarps) {
        if (lane == 0) {
            const int row0 = cta * kKeysPerCta;
            mbar_expect_tx(barFull, kSlotBytes + 8192);
            tma_2d(sRing, &tmWq, cta * kColsPerCta, 0, barFull);
            tma_2d(sRing + 16384, &tmWq, cta * kColsPerCta, 256, barFull);
            bulk_1d(sA, x, 8192, barFull);
            for (int i = 1; i < kItems; ++i) {
                const int s = i % kSlots, u = i / kSlots;
                const uint32_t full = barFull + s * 8, dst = sRing + s * kSlotBytes;
                mbar_wait(barEmpty + s * 8, (u & 1) ^ 1);
                mbar_expect_tx(full, kSlotBytes);
                if (i < kItems - 1) {
                    const int r = row0 + ((i - 1) >> 1) * kTileKeys;
                    const CUtensorMap* tm = ((i - 1) & 1) ? &tmV : &tmK;
                    tma_2d(dst, tm, 0, r, full);
                    tma_2d(dst + 16384, tm, 64, r, full);
                } else {
                    const int c0 = (cta & 15) * kColsPerCta, r = (cta >> 4) * 512;
                    tma_2d(dst, &tmWo, c0, r, full);
                    tma_2d(dst + 16384, &tmWo, c0, r + 256, full);
                }
            }
        }
        return;
    }

    const int g = lane >> 2, t = lane & 3;
    const int unit = cta >> 1;
    const int b_att = unit >> 3, kvh_att = unit & 7;

    mbar_wait(barFull, 0);
    gemv_8x512x32(sA, sRing, sRed, warp, lane);
    __syncwarp();
    if (lane == 0) mbar_arrive(barEmpty);
    consumer_bar();
    {
        int col, row;
        const float v = gemv_reduce(sRed, tid, col, row);
        g_q[row * kHqDh + cta * kColsPerCta + col] = __float2bfloat16_rn(v);
    }
    consumer_bar();
    if (tid == 0) {
        __threadfence();
        red_release_add(&g_qcount[cta >> 4], 1u);
        spin_until(&g_qcount[kvh_att], 16u);
    }
    consumer_bar();

    uint32_t qa[8][2];
    {
        const unsigned* qp = reinterpret_cast<const unsigned*>(g_q + b_att * kHqDh + kvh_att * 512 + (g & 3) * kDh);
#pragma unroll
        for (int kk = 0; kk < 8; ++kk) {
            const unsigned v0 = __ldcg(qp + kk * 8 + t);
            const unsigned v1 = __ldcg(qp + kk * 8 + t + 4);
            qa[kk][0] = (g < 4) ? v0 : 0u;
            qa[kk][1] = (g < 4) ? v1 : 0u;
        }
    }

    constexpr float kScaleLog2 = 0.08838834764831845f * 1.4426950408889634f;
    float o[16][4];
#pragma unroll
    for (int j = 0; j < 16; ++j) { o[j][0] = o[j][1] = o[j][2] = o[j][3] = 0.f; }
    float m_run = -INFINITY, l_run = 0.f;

    const uint32_t kRow = (warp * 16 + (lane & 7)) * 128;
    const uint32_t kSw0 = (uint32_t)((((lane >> 3)) ^ (lane & 7)) << 4);
    const uint32_t kSw1 = (uint32_t)(((4 + (lane >> 3)) ^ (lane & 7)) << 4);
    const uint32_t vRow = (warp * 16 + (lane & 7) + 8 * ((lane >> 3) & 1)) * 128;

    for (int tile = 0; tile < kTiles; ++tile) {
        const int iK = 1 + 2 * tile, iV = iK + 1;
        const int sK = iK % kSlots, sV = iV % kSlots;
        const uint32_t aK = sRing + sK * kSlotBytes, aV = sRing + sV * kSlotBytes;

        mbar_wait(barFull + sK * 8, (iK / kSlots) & 1);
        float s[2][4] = {{0.f, 0.f, 0.f, 0.f}, {0.f, 0.f, 0.f, 0.f}};
#pragma unroll
        for (int q4 = 0; q4 < 4; ++q4) {
            const uint32_t base = aK + (q4 >> 1) * 16384 + kRow + ((q4 & 1) ? kSw1 : kSw0);
#pragma unroll
            for (int nt = 0; nt < 2; ++nt) {
                uint32_t kb[4];
                ldsm_x4(kb, base + nt * 1024);
                mma_bf16(s[nt], qa[2 * q4][0], 0u, qa[2 * q4][1], 0u, kb[0], kb[1]);
                mma_bf16(s[nt], qa[2 * q4 + 1][0], 0u, qa[2 * q4 + 1][1], 0u, kb[2], kb[3]);
            }
        }
        __syncwarp();
        if (lane == 0) mbar_arrive(barEmpty + sK * 8);

        float mx = fmaxf(fmaxf(s[0][0], s[0][1]), fmaxf(s[1][0], s[1][1])) * kScaleLog2;
        mx = fmaxf(mx, __shfl_xor_sync(0xffffffffu, mx, 1));
        mx = fmaxf(mx, __shfl_xor_sync(0xffffffffu, mx, 2));
        const float m_new = fmaxf(m_run, mx);
        const float alpha = exp2f(m_run - m_new);
        const float p00 = exp2f(fmaf(s[0][0], kScaleLog2, -m_new));
        const float p01 = exp2f(fmaf(s[0][1], kScaleLog2, -m_new));
        const float p10 = exp2f(fmaf(s[1][0], kScaleLog2, -m_new));
        const float p11 = exp2f(fmaf(s[1][1], kScaleLog2, -m_new));
        m_run = m_new;
        l_run = l_run * alpha + ((p00 + p01) + (p10 + p11));
#pragma unroll
        for (int j = 0; j < 16; ++j) { o[j][0] *= alpha; o[j][1] *= alpha; }
        const uint32_t pa0 = pack_bf16(p00, p01), pa2 = pack_bf16(p10, p11);

        mbar_wait(barFull + sV * 8, (iV / kSlots) & 1);
#pragma unroll
        for (int p = 0; p < 8; ++p) {
            const int chunk = 2 * p + (lane >> 4);
            uint32_t vb[4];
            ldsm_x4_t(vb, aV + (chunk >> 3) * 16384 + vRow + (((chunk & 7) ^ (lane & 7)) << 4));
            mma_bf16(o[2 * p], pa0, 0u, pa2, 0u, vb[0], vb[1]);
            mma_bf16(o[2 * p + 1], pa0, 0u, pa2, 0u, vb[2], vb[3]);
        }
        __syncwarp();
        if (lane == 0) mbar_arrive(barEmpty + sV * 8);
    }

    l_run += __shfl_xor_sync(0xffffffffu, l_run, 1);
    l_run += __shfl_xor_sync(0xffffffffu, l_run, 2);
    if (g < 4) {
        float* dst = sWO + (warp * 4 + g) * kDh + 2 * t;
#pragma unroll
        for (int j = 0; j < 16; ++j) *reinterpret_cast<float2*>(dst + 8 * j) = make_float2(o[j][0], o[j][1]);
        if (t == 0) { sML[warp * 8 + g] = m_run; sML[warp * 8 + 4 + g] = l_run; }
    }
    consumer_bar();
    {
        const int h = tid >> 6, d2 = (tid & 63) * 2;
        float M = -INFINITY;
#pragma unroll
        for (int w = 0; w < 8; ++w) M = fmaxf(M, sML[w * 8 + h]);
        float ox = 0.f, oy = 0.f, L = 0.f;
#pragma unroll
        for (int w = 0; w < 8; ++w) {
            const float sc = exp2f(sML[w * 8 + h] - M);
            const float2 v = *reinterpret_cast<const float2*>(sWO + (w * 4 + h) * kDh + d2);
            ox = fmaf(sc, v.x, ox);
            oy = fmaf(sc, v.y, oy);
            L = fmaf(sc, sML[w * 8 + 4 + h], L);
        }
        *reinterpret_cast<float2*>(&g_partO[cta][h * kDh + d2]) = make_float2(ox, oy);
        if ((tid & 63) == 0) { g_partML[cta][h] = M; g_partML[cta][4 + h] = L; }
    }
    consumer_bar();
    const int kvh_t = cta >> 4, cg = cta & 15;
    if (tid == 0) {
        __threadfence();
        red_release_add(&g_pcount[kvh_att], 1u);
        spin_until(&g_pcount[kvh_t], 16u);
        const unsigned old = atomicAdd(&g_done, 1u);
        if (old == kCTAs - 1) {
            for (int i = 0; i < kHkv; ++i) { g_qcount[i] = 0u; g_pcount[i] = 0u; }
            g_done = 0u;
        }
    }
    consumer_bar();
    {
        const int bb = tid >> 5, r = tid & 31;
        const int h = r >> 3;
        const int c0 = (bb * 8 + kvh_t) * 2;
        const float m0 = __ldcg(&g_partML[c0][h]), l0 = __ldcg(&g_partML[c0][4 + h]);
        const float m1 = __ldcg(&g_partML[c0 + 1][h]), l1 = __ldcg(&g_partML[c0 + 1][4 + h]);
        const float4* p0 = reinterpret_cast<const float4*>(&g_partO[c0][16 * r]);
        const float4* p1 = reinterpret_cast<const float4*>(&g_partO[c0 + 1][16 * r]);
        float4 a0[4], a1[4];
#pragma unroll
        for (int i = 0; i < 4; ++i) { a0[i] = __ldcg(p0 + i); a1[i] = __ldcg(p1 + i); }
        const float M = fmaxf(m0, m1);
        float w0 = exp2f(m0 - M), w1 = exp2f(m1 - M);
        const float inv = 1.0f / (w0 * l0 + w1 * l1);
        w0 *= inv; w1 *= inv;
        uint32_t pk[8];
#pragma unroll
        for (int i = 0; i < 4; ++i) {
            pk[2 * i] = pack_bf16(fmaf(w0, a0[i].x, w1 * a1[i].x), fmaf(w0, a0[i].y, w1 * a1[i].y));
            pk[2 * i + 1] = pack_bf16(fmaf(w0, a0[i].z, w1 * a1[i].z), fmaf(w0, a0[i].w, w1 * a1[i].w));
        }
        uint4* dst = reinterpret_cast<uint4*>(smem + kOffA + (bb * 512 + 16 * r) * 2);
        dst[0] = make_uint4(pk[0], pk[1], pk[2], pk[3]);
        dst[1] = make_uint4(pk[4], pk[5], pk[6], pk[7]);
    }
    {
        constexpr int iW = kItems - 1;
        mbar_wait(barFull + (iW % kSlots) * 8, (iW / kSlots) & 1);
    }
    consumer_bar();
    gemv_8x512x32(sA, sRing + ((kItems - 1) % kSlots) * kSlotBytes, sRed, warp, lane);
    consumer_bar();
    int ocol, orow;
    {
        const float y = gemv_reduce(sRed, tid, ocol, orow);
        g_partY[kvh_t][orow][cg * kColsPerCta + ocol] = y;
    }
    consumer_bar();
    if (tid == 0) {
        __threadfence();
        const unsigned old = atomicAdd(&g_fcount[cg], 1u);
        const unsigned last = (old == kHkv - 1) ? 1u : 0u;
        if (last) g_fcount[cg] = 0u;
        __threadfence();
        *sFlag = last;
    }
    consumer_bar();
    if (*sFlag) {
        float y = 0.f;
#pragma unroll
        for (int k = 0; k < kHkv; ++k) y += __ldcg(&g_partY[k][orow][cg * kColsPerCta + ocol]);
        out[orow * kD + cg * kColsPerCta + ocol] = __float2bfloat16_rn(y);
    }
}

typedef CUresult (*EncodeTiledFn)(CUtensorMap*, CUtensorMapDataType, cuuint32_t, void*, const cuuint64_t*,
                                  const cuuint64_t*, const cuuint32_t*, const cuuint32_t*, CUtensorMapInterleave,
                                  CUtensorMapSwizzle, CUtensorMapL2promotion, CUtensorMapFloatOOBfill);

bool encode_2d(EncodeTiledFn fn, CUtensorMap* tm, const void* base, uint64_t cols, uint64_t rows, uint64_t pitch_bytes,
               uint32_t box_cols, uint32_t box_rows, CUtensorMapSwizzle sw, CUtensorMapL2promotion promo) {
    cuuint64_t dims[2] = {cols, rows};
    cuuint64_t strides[1] = {pitch_bytes};
    cuuint32_t box[2] = {box_cols, box_rows};
    cuuint32_t estr[2] = {1, 1};
    return fn(tm, CU_TENSOR_MAP_DATA_TYPE_BFLOAT16, 2, const_cast<void*>(base), dims, strides, box, estr,
              CU_TENSOR_MAP_INTERLEAVE_NONE, sw, promo, CU_TENSOR_MAP_FLOAT_OOB_FILL_NONE) == CUDA_SUCCESS;
}

}

extern "C" void kernel_launch(void* const* d_in, const int* in_sizes, int n_in, void* d_out, int out_size) {
    (void)in_sizes; (void)n_in; (void)out_size;
    const __nv_bfloat16* x = (const __nv_bfloat16*)d_in[0];
    const void* kc = d_in[1];
    const void* vc = d_in[2];
    const void* wq = d_in[3];
    const void* wo = d_in[4];

    void* fnp = nullptr;
    cudaDriverEntryPointQueryResult qres;
    if (cudaGetDriverEntryPoint("cuTensorMapEncodeTiled", &fnp, cudaEnableDefault, &qres) != cudaSuccess || !fnp) return;
    EncodeTiledFn fn = (EncodeTiledFn)fnp;

    CUtensorMap tmK, tmV, tmWq, tmWo;
    const uint64_t rows = (uint64_t)kB * kHkv * kSk;
    if (!encode_2d(fn, &tmK, kc, kDh, rows, kDh * 2, 64, kTileKeys, CU_TENSOR_MAP_SWIZZLE_128B, CU_TENSOR_MAP_L2_PROMOTION_L2_256B)) return;
    if (!encode_2d(fn, &tmV, vc, kDh, rows, kDh * 2, 64, kTileKeys, CU_TENSOR_MAP_SWIZZLE_128B, CU_TENSOR_MAP_L2_PROMOTION_L2_256B)) return;
    if (!encode_2d(fn, &tmWq, wq, kHqDh, kD, kHqDh * 2, kColsPerCta, 256, CU_TENSOR_MAP_SWIZZLE_NONE, CU_TENSOR_MAP_L2_PROMOTION_L2_128B)) return;
    if (!encode_2d(fn, &tmWo, wo, kD, kHqDh, kD * 2, kColsPerCta, 256, CU_TENSOR_MAP_SWIZZLE_NONE, CU_TENSOR_MAP_L2_PROMOTION_L2_128B)) return;

    cudaFuncSetAttribute(gqa_decode_fused, cudaFuncAttributeMaxDynamicSharedMemorySize, kSmemBytes);
    gqa_decode_fused<<<kCTAs, kThreads, kSmemBytes>>>(tmK, tmV, tmWq, tmWo, x, (__nv_bfloat16*)d_out);
}
```

```cpp
#include <cuda_runtime.h>
#include <cuda_bf16.h>
#include <cuda.h>
#include <stdint.h>

namespace {

constexpr int kB = 8, kHkv = 8, kSk = 8192, kDh = 128, kD = 512, kHqDh = 4096;
constexpr int kSplits = 2;
constexpr int kCTAs = kB * kHkv * kSplits;
constexpr int kKeysPerCta = kSk / kSplits;
constexpr int kTileKeys = 128;
constexpr int kTiles = kKeysPerCta / kTileKeys;
constexpr int kSlotBytes = kTileKeys * kDh * 2;
constexpr int kSlots = 6;
constexpr int kConsumerWarps = 8;
constexpr int kThreads = (kConsumerWarps + 1) * 32;
constexpr int kItems = 2 * kTiles + 2;
constexpr int kColsPerCta = 32;
constexpr int kPace = 2;
constexpr unsigned kSpinLimit = 1u << 22;

constexpr int kOffRing = 0;
constexpr int kAPitch  = 1040;
constexpr int kOffA    = kSlots * kSlotBytes;
constexpr int kOffWO   = kOffA + 8 * kAPitch;
constexpr int kOffML   = kOffWO + 16384;
constexpr int kOffQ    = kOffML + 256;
constexpr int kOffBar  = kOffQ + 1024;
constexpr int kOffTag  = kOffBar + 2 * kSlots * 8;
constexpr int kSmemBytes = kOffTag + 16 + 1024;

__device__ unsigned g_qx[kB * kHqDh];
__device__ unsigned g_partO[kCTAs][4 * kDh];
__device__ unsigned long long g_partML[kCTAs][8];
__device__ unsigned g_partY[kHkv][kB][kD];
__device__ unsigned long long g_state;
#define DBG_T(i) do {} while (0)

__device__ __forceinline__ uint32_t smem_u32(const void* p) { return (uint32_t)__cvta_generic_to_shared(p); }

__device__ __forceinline__ void mbar_init(uint32_t bar, uint32_t cnt) {
    asm volatile("mbarrier.init.shared::cta.b64 [%0], %1;" ::"r"(bar), "r"(cnt) : "memory");
}
__device__ __forceinline__ void mbar_expect_tx(uint32_t bar, uint32_t bytes) {
    asm volatile("mbarrier.arrive.expect_tx.shared::cta.b64 _, [%0], %1;" ::"r"(bar), "r"(bytes) : "memory");
}
__device__ __forceinline__ void mbar_arrive(uint32_t bar) {
    asm volatile("mbarrier.arrive.shared::cta.b64 _, [%0];" ::"r"(bar) : "memory");
}
__device__ __forceinline__ bool mbar_try_wait(uint32_t bar, uint32_t parity) {
    uint32_t ok;
    asm volatile(
        "{\n.reg .pred p;\n"
        "mbarrier.try_wait.parity.shared::cta.b64 p, [%1], %2;\n"
        "selp.u32 %0, 1, 0, p;\n}"
        : "=r"(ok) : "r"(bar), "r"(parity) : "memory");
    return ok != 0;
}
__device__ __forceinline__ void mbar_wait(uint32_t bar, uint32_t parity) {
    for (unsigned it = 0; !mbar_try_wait(bar, parity); ++it) {
        if (it > (1u << 26)) __trap();
    }
}
__device__ __forceinline__ void tma_2d(uint32_t dst, const CUtensorMap* tm, int c0, int c1, uint32_t bar) {
    asm volatile(
        "cp.async.bulk.tensor.2d.shared::cluster.global.mbarrier::complete_tx::bytes [%0], [%1, {%3, %4}], [%2];"
        ::"r"(dst), "l"((uint64_t)tm), "r"(bar), "r"(c0), "r"(c1) : "memory");
}
__device__ __forceinline__ void bulk_1d(uint32_t dst, const void* src, uint32_t bytes, uint32_t bar) {
    asm volatile(
        "cp.async.bulk.shared::cluster.global.mbarrier::complete_tx::bytes [%0], [%1], %2, [%3];"
        ::"r"(dst), "l"(src), "r"(bytes), "r"(bar) : "memory");
}
__device__ __forceinline__ void ldsm_x4(uint32_t (&r)[4], uint32_t addr) {
    asm volatile("ldmatrix.sync.aligned.m8n8.x4.shared.b16 {%0,%1,%2,%3}, [%4];"
                 : "=r"(r[0]), "=r"(r[1]), "=r"(r[2]), "=r"(r[3]) : "r"(addr) : "memory");
}
__device__ __forceinline__ void ldsm_x4_t(uint32_t (&r)[4], uint32_t addr) {
    asm volatile("ldmatrix.sync.aligned.m8n8.x4.trans.shared.b16 {%0,%1,%2,%3}, [%4];"
                 : "=r"(r[0]), "=r"(r[1]), "=r"(r[2]), "=r"(r[3]) : "r"(addr) : "memory");
}
__device__ __forceinline__ void mma_bf16(float (&c)[4], uint32_t a0, uint32_t a1, uint32_t a2, uint32_t a3,
                                         uint32_t b0, uint32_t b1) {
    asm volatile(
        "mma.sync.aligned.m16n8k16.row.col.f32.bf16.bf16.f32 {%0,%1,%2,%3}, {%4,%5,%6,%7}, {%8,%9}, {%0,%1,%2,%3};"
        : "+f"(c[0]), "+f"(c[1]), "+f"(c[2]), "+f"(c[3])
        : "r"(a0), "r"(a1), "r"(a2), "r"(a3), "r"(b0), "r"(b1));
}
__device__ __forceinline__ uint32_t pack_bf16(float lo, float hi) {
    __nv_bfloat162 v = __floats2bfloat162_rn(lo, hi);
    return *reinterpret_cast<uint32_t*>(&v);
}
__device__ __forceinline__ void consumer_bar() { asm volatile("bar.sync 1, 256;" ::: "memory"); }
__device__ __forceinline__ void st_relaxed_u32(unsigned* p, unsigned v) {
    asm volatile("st.relaxed.gpu.global.u32 [%0], %1;" ::"l"(p), "r"(v) : "memory");
}
__device__ __forceinline__ void st_relaxed_v2(unsigned* p, unsigned a, unsigned b) {
    asm volatile("st.relaxed.gpu.global.v2.u32 [%0], {%1, %2};" ::"l"(p), "r"(a), "r"(b) : "memory");
}
__device__ __forceinline__ void st_relaxed_u64(unsigned long long* p, unsigned long long v) {
    asm volatile("st.relaxed.gpu.global.u64 [%0], %1;" ::"l"(p), "l"(v) : "memory");
}
__device__ __forceinline__ unsigned ld_relaxed_u32(const unsigned* p) {
    unsigned v;
    asm volatile("ld.relaxed.gpu.global.u32 %0, [%1];" : "=r"(v) : "l"(p) : "memory");
    return v;
}
__device__ __forceinline__ uint2 ld_relaxed_v2(const unsigned* p) {
    uint2 v;
    asm volatile("ld.relaxed.gpu.global.v2.u32 {%0, %1}, [%2];" : "=r"(v.x), "=r"(v.y) : "l"(p) : "memory");
    return v;
}
__device__ __forceinline__ uint4 ld_relaxed_v4(const unsigned* p) {
    uint4 v;
    asm volatile("ld.relaxed.gpu.global.v4.u32 {%0, %1, %2, %3}, [%4];"
                 : "=r"(v.x), "=r"(v.y), "=r"(v.z), "=r"(v.w) : "l"(p) : "memory");
    return v;
}
__device__ __forceinline__ unsigned long long ld_relaxed_u64(const unsigned long long* p) {
    unsigned long long v;
    asm volatile("ld.relaxed.gpu.global.u64 %0, [%1];" : "=l"(v) : "l"(p) : "memory");
    return v;
}
__device__ __forceinline__ unsigned tag_f32(float v, unsigned tag8) { return (__float_as_uint(v) & 0xFFFFFF00u) | tag8; }
__device__ __forceinline__ float untag_f32(unsigned w) { return __uint_as_float(w & 0xFFFFFF00u); }

__device__ __forceinline__ void gemv_8x512x32(uint32_t sA, uint32_t sW, float* red, int warp, int lane) {
    float c[2][4] = {{0.f, 0.f, 0.f, 0.f}, {0.f, 0.f, 0.f, 0.f}};
    const int g = lane >> 2, t = lane & 3;
#pragma unroll
    for (int ks = 0; ks < 4; ++ks) {
        const int k0 = warp * 64 + ks * 16;
        uint32_t b0, b1;
        asm volatile("ld.shared.b32 %0, [%1];" : "=r"(b0) : "r"(sA + g * kAPitch + (k0 + 2 * t) * 2) : "memory");
        asm volatile("ld.shared.b32 %0, [%1];" : "=r"(b1) : "r"(sA + g * kAPitch + (k0 + 2 * t + 8) * 2) : "memory");
#pragma unroll
        for (int mt = 0; mt < 2; ++mt) {
            uint32_t a[4];
            const int krow = k0 + (lane & 7) + 8 * (lane >> 4);
            const int chunk = 2 * mt + ((lane >> 3) & 1);
            ldsm_x4_t(a, sW + krow * 64 + ((chunk ^ ((krow >> 1) & 3)) << 4));
            mma_bf16(c[mt], a[0], a[1], a[2], a[3], b0, b1);
        }
    }
    float* r = red + warp * (8 * 36) + (2 * t) * 36 + g;
#pragma unroll
    for (int mt = 0; mt < 2; ++mt) {
        r[16 * mt] = c[mt][0];
        r[36 + 16 * mt] = c[mt][1];
        r[16 * mt + 8] = c[mt][2];
        r[36 + 16 * mt + 8] = c[mt][3];
    }
}
__device__ __forceinline__ float gemv_reduce(const float* red, int j) {
    const float* r = red + (j >> 5) * 36 + (j & 31);
    float s = 0.f;
#pragma unroll
    for (int w = 0; w < 8; ++w) s += r[w * (8 * 36)];
    return s;
}

__device__ __forceinline__ void tail_phase(const int tid, uint8_t* smem, const int cta, const unsigned epoch,
                                           __nv_bfloat16* __restrict__ out) {
    const uint32_t sbase = smem_u32(smem);
    const uint32_t sRing = sbase + kOffRing;
    const uint32_t sA = sbase + kOffA;
    const uint32_t barFull = sbase + kOffBar;
    float* sRed = reinterpret_cast<float*>(smem + kOffWO);
    float* sWO = reinterpret_cast<float*>(smem + kOffWO);
    float* sML = reinterpret_cast<float*>(smem + kOffML);
    const int warp = tid >> 5, lane = tid & 31;
    const unsigned tag8 = epoch & 0xFFu;
    consumer_bar();
    {
        const int h = tid >> 6, d2 = (tid & 63) * 2;
        float M = -INFINITY;
#pragma unroll
        for (int w = 0; w < 8; ++w) M = fmaxf(M, sML[w * 8 + h]);
        float ox = 0.f, oy = 0.f, L = 0.f;
#pragma unroll
        for (int w = 0; w < 8; ++w) {
            const float sc = exp2f(sML[w * 8 + h] - M);
            const float2 v = *reinterpret_cast<const float2*>(sWO + (w * 4 + h) * kDh + d2);
            ox = fmaf(sc, v.x, ox);
            oy = fmaf(sc, v.y, oy);
            L = fmaf(sc, sML[w * 8 + 4 + h], L);
        }
        st_relaxed_v2(&g_partO[cta][h * kDh + d2], tag_f32(ox, tag8), tag_f32(oy, tag8));
        if ((tid & 63) == 0 && h < 3) {
            st_relaxed_u64(&g_partML[cta][h], (unsigned long long)__float_as_uint(M) | ((unsigned long long)epoch << 32));
            st_relaxed_u64(&g_partML[cta][4 + h], (unsigned long long)__float_as_uint(L) | ((unsigned long long)epoch << 32));
        }
        consumer_bar();
        if (tid == 192) {
            st_relaxed_u64(&g_partML[cta][3], (unsigned long long)__float_as_uint(M) | ((unsigned long long)epoch << 32));
            st_relaxed_u64(&g_partML[cta][7], (unsigned long long)__float_as_uint(L) | ((unsigned long long)epoch << 32));
        }
    }
    DBG_T(5);
    const int kvh_t = cta >> 4, cg = cta & 15;
    {
        const int bb = warp;
        const int c0 = (bb * 8 + kvh_t) * 2;
        if (lane < 2) {
            for (unsigned it = 0; (unsigned)(ld_relaxed_u64(&g_partML[c0 + lane][7]) >> 32) != epoch && it < kSpinLimit; ++it) __nanosleep(40);
        }
        __syncwarp();
        DBG_T(6);
        uint4 a0[4], a1[4];
        unsigned long long ml[4];
        for (unsigned it = 0; it < kSpinLimit; ++it) {
#pragma unroll
            for (int h = 0; h < 4; ++h) {
                a0[h] = ld_relaxed_v4(&g_partO[c0][kDh * h + 4 * lane]);
                a1[h] = ld_relaxed_v4(&g_partO[c0 + 1][kDh * h + 4 * lane]);
            }
            ml[0] = ld_relaxed_u64(&g_partML[c0][lane & 3]);
            ml[1] = ld_relaxed_u64(&g_partML[c0][4 + (lane & 3)]);
            ml[2] = ld_relaxed_u64(&g_partML[c0 + 1][lane & 3]);
            ml[3] = ld_relaxed_u64(&g_partML[c0 + 1][4 + (lane & 3)]);
            unsigned bad = 0u;
#pragma unroll
            for (int h = 0; h < 4; ++h) {
                bad |= (a0[h].x ^ tag8) | (a0[h].y ^ tag8) | (a0[h].z ^ tag8) | (a0[h].w ^ tag8);
                bad |= (a1[h].x ^ tag8) | (a1[h].y ^ tag8) | (a1[h].z ^ tag8) | (a1[h].w ^ tag8);
            }
            bad &= 0xFFu;
#pragma unroll
            for (int i = 0; i < 4; ++i) bad |= (unsigned)(ml[i] >> 32) ^ epoch;
            if (bad == 0u) break;
        }
        DBG_T(11);
        const float m0 = __uint_as_float((unsigned)ml[0]), l0 = __uint_as_float((unsigned)ml[1]);
        const float m1 = __uint_as_float((unsigned)ml[2]), l1 = __uint_as_float((unsigned)ml[3]);
        const float M = fmaxf(m0, m1);
        float w0 = exp2f(m0 - M), w1 = exp2f(m1 - M);
        const float inv = __fdividef(1.0f, w0 * l0 + w1 * l1);
        w0 *= inv; w1 *= inv;
        uint8_t* dst = smem + kOffA + bb * kAPitch + 8 * lane;
#pragma unroll
        for (int h = 0; h < 4; ++h) {
            const float u0 = __shfl_sync(0xffffffffu, w0, h), u1 = __shfl_sync(0xffffffffu, w1, h);
            const uint32_t lo = pack_bf16(fmaf(u0, untag_f32(a0[h].x), u1 * untag_f32(a1[h].x)),
                                          fmaf(u0, untag_f32(a0[h].y), u1 * untag_f32(a1[h].y)));
            const uint32_t hi = pack_bf16(fmaf(u0, untag_f32(a0[h].z), u1 * untag_f32(a1[h].z)),
                                          fmaf(u0, untag_f32(a0[h].w), u1 * untag_f32(a1[h].w)));
            *reinterpret_cast<uint2*>(dst + h * (kDh * 2)) = make_uint2(lo, hi);
        }
    }
    DBG_T(12);
    {
        constexpr int iW = kItems - 1;
        mbar_wait(barFull + (iW % kSlots) * 8, (iW / kSlots) & 1);
    }
    DBG_T(13);
    consumer_bar();
    DBG_T(7);
    gemv_8x512x32(sA, sRing + ((kItems - 1) % kSlots) * kSlotBytes, sRed, warp, lane);
    consumer_bar();
    DBG_T(8);
    const unsigned yw = tag_f32(gemv_reduce(sRed, tid), tag8);
    unsigned* yp = &g_partY[0][warp][cg * kColsPerCta + lane];
    if (kvh_t != (cg & 7)) {
        st_relaxed_u32(yp + kvh_t * (kB * kD), yw);
    } else {
        unsigned w[kHkv];
        for (unsigned it = 0; it < kSpinLimit; ++it) {
            unsigned bad = 0u;
#pragma unroll
            for (int k = 0; k < kHkv; ++k) w[k] = (k == kvh_t) ? yw : ld_relaxed_u32(yp + k * (kB * kD));
#pragma unroll
            for (int k = 0; k < kHkv; ++k) bad |= (w[k] ^ tag8) & 0xFFu;
            if (bad == 0u) break;
            __nanosleep(20);
        }
        float y = 0.f;
#pragma unroll
        for (int k = 0; k < kHkv; ++k) y += untag_f32(w[k]);
        out[warp * kD + cg * kColsPerCta + lane] = __float2bfloat16_rn(y);
    }
}

__global__ void __launch_bounds__(kThreads, 1)
gqa_decode_fused(const __grid_constant__ CUtensorMap tmK, const __grid_constant__ CUtensorMap tmV,
                 const __grid_constant__ CUtensorMap tmWq, const __grid_constant__ CUtensorMap tmWo,
                 const __nv_bfloat16* __restrict__ x, __nv_bfloat16* __restrict__ out) {
    extern __shared__ uint8_t smem_raw[];
    uint8_t* smem = reinterpret_cast<uint8_t*>((reinterpret_cast<uintptr_t>(smem_raw) + 1023) & ~(uintptr_t)1023);
    const uint32_t sbase = smem_u32(smem);
    const uint32_t sRing = sbase + kOffRing;
    const uint32_t sA = sbase + kOffA;
    const uint32_t barFull = sbase + kOffBar;
    const uint32_t barEmpty = barFull + kSlots * 8;
    float* sRed = reinterpret_cast<float*>(smem + kOffWO);
    float* sWO = reinterpret_cast<float*>(smem + kOffWO);
    float* sML = reinterpret_cast<float*>(smem + kOffML);
    uint32_t* sQ = reinterpret_cast<uint32_t*>(smem + kOffQ);
    volatile unsigned* sTag = reinterpret_cast<volatile unsigned*>(smem + kOffTag);

    const int tid = threadIdx.x, warp = tid >> 5, lane = tid & 31;
    const int cta = blockIdx.x;

    if (tid == 0) {
        for (int i = 0; i < kSlots; ++i) {
            mbar_init(barFull + i * 8, 1);
            mbar_init(barEmpty + i * 8, kConsumerWarps);
        }
        *sTag = 0u;
        asm volatile("fence.mbarrier_init.release.cluster;" ::: "memory");
    }
    __syncthreads();

    if (warp == kConsumerWarps) {
        if (lane == 0) {
            const int row0 = cta * kKeysPerCta;
            mbar_expect_tx(barFull, kSlotBytes + 8192);
            tma_2d(sRing, &tmWq, cta * kColsPerCta, 0, barFull);
            tma_2d(sRing + 16384, &tmWq, cta * kColsPerCta, 256, barFull);
            for (int r = 0; r < kB; ++r) bulk_1d(sA + r * kAPitch, x + r * kD, kD * 2, barFull);
            for (int i = 1; i < kItems; ++i) {
                const int s = i % kSlots, u = i / kSlots;
                const uint32_t full = barFull + s * 8, dst = sRing + s * kSlotBytes;
                mbar_wait(barEmpty + s * 8, (u & 1) ^ 1);
                const int dep = (i == kItems - 1) ? 1 : kPace;
                if (i >= dep) mbar_wait(barFull + ((i - dep) % kSlots) * 8, ((i - dep) / kSlots) & 1);
                mbar_expect_tx(full, kSlotBytes);
                if (i < kItems - 1) {
                    const int r = row0 + ((i - 1) >> 1) * kTileKeys;
                    const CUtensorMap* tm = ((i - 1) & 1) ? &tmV : &tmK;
                    tma_2d(dst, tm, 0, r, full);
                    tma_2d(dst + 16384, tm, 64, r, full);
                } else {
                    const int c0 = (cta & 15) * kColsPerCta, r = (cta >> 4) * 512;
                    tma_2d(dst, &tmWo, c0, r, full);
                    tma_2d(dst + 16384, &tmWo, c0, r + 256, full);
                }
            }
        } else if (lane == 1) {
            const unsigned long long old = atomicAdd(&g_state, 1ull);
            if ((unsigned)old == kCTAs - 1) atomicAdd(&g_state, (1ull << 32) - kCTAs);
            *sTag = (unsigned)(old >> 32) + 1u;
        }
        return;
    }

    const int g = lane >> 2, t = lane & 3;
    const int unit = cta >> 1;
    const int b_att = unit >> 3, kvh_att = unit & 7;

    DBG_T(0);
    mbar_wait(barFull, 0);
    DBG_T(1);
    gemv_8x512x32(sA, sRing, sRed, warp, lane);
    __syncwarp();
    if (lane == 0) mbar_arrive(barEmpty);
    consumer_bar();
    unsigned epoch;
    for (unsigned it = 0; (epoch = *sTag) == 0u && it < kSpinLimit; ++it) {}
    const unsigned tag16 = epoch & 0xFFFFu;
    {
        const float v = gemv_reduce(sRed, tid);
        const unsigned w = (unsigned)__bfloat16_as_ushort(__float2bfloat16_rn(v)) | (tag16 << 16);
        st_relaxed_u32(&g_qx[warp * kHqDh + cta * kColsPerCta + lane], w);
    }
    DBG_T(2);
    {
        const unsigned* src = &g_qx[b_att * kHqDh + kvh_att * 512 + 2 * tid];
        uint2 w = ld_relaxed_v2(src);
        for (unsigned it = 0; (((w.x >> 16) != tag16) | ((w.y >> 16) != tag16)) && it < kSpinLimit; ++it) w = ld_relaxed_v2(src);
        sQ[tid] = (w.x & 0xFFFFu) | (w.y << 16);
    }
    consumer_bar();
    DBG_T(3);

    uint32_t qa[8][2];
#pragma unroll
    for (int kk = 0; kk < 8; ++kk) {
        const uint32_t v0 = sQ[(g & 3) * 64 + kk * 8 + t];
        const uint32_t v1 = sQ[(g & 3) * 64 + kk * 8 + t + 4];
        qa[kk][0] = (g < 4) ? v0 : 0u;
        qa[kk][1] = (g < 4) ? v1 : 0u;
    }

    constexpr float kScaleLog2 = 0.08838834764831845f * 1.4426950408889634f;
    float o[16][4];
#pragma unroll
    for (int j = 0; j < 16; ++j) { o[j][0] = o[j][1] = o[j][2] = o[j][3] = 0.f; }
    float m_run = -INFINITY, l_run = 0.f;

    const uint32_t kRow = (warp * 16 + (lane & 7)) * 128;
    const uint32_t kSw0 = (uint32_t)((((lane >> 3)) ^ (lane & 7)) << 4);
    const uint32_t kSw1 = (uint32_t)(((4 + (lane >> 3)) ^ (lane & 7)) << 4);
    const uint32_t vRow = (warp * 16 + (lane & 7) + 8 * ((lane >> 3) & 1)) * 128;

    for (int tile = 0; tile < kTiles; ++tile) {
        const int iK = 1 + 2 * tile, iV = iK + 1;
        const int sK = iK % kSlots, sV = iV % kSlots;
        const uint32_t aK = sRing + sK * kSlotBytes, aV = sRing + sV * kSlotBytes;

        mbar_wait(barFull + sK * 8, (iK / kSlots) & 1);
        float s[2][4] = {{0.f, 0.f, 0.f, 0.f}, {0.f, 0.f, 0.f, 0.f}};
#pragma unroll
        for (int q4 = 0; q4 < 4; ++q4) {
            const uint32_t base = aK + (q4 >> 1) * 16384 + kRow + ((q4 & 1) ? kSw1 : kSw0);
#pragma unroll
            for (int nt = 0; nt < 2; ++nt) {
                uint32_t kb[4];
                ldsm_x4(kb, base + nt * 1024);
                mma_bf16(s[nt], qa[2 * q4][0], 0u, qa[2 * q4][1], 0u, kb[0], kb[1]);
                mma_bf16(s[nt], qa[2 * q4 + 1][0], 0u, qa[2 * q4 + 1][1], 0u, kb[2], kb[3]);
            }
        }
        __syncwarp();
        if (lane == 0) mbar_arrive(barEmpty + sK * 8);

        float mx = fmaxf(fmaxf(s[0][0], s[0][1]), fmaxf(s[1][0], s[1][1])) * kScaleLog2;
        mx = fmaxf(mx, __shfl_xor_sync(0xffffffffu, mx, 1));
        mx = fmaxf(mx, __shfl_xor_sync(0xffffffffu, mx, 2));
        const float m_new = fmaxf(m_run, mx);
        const float alpha = exp2f(m_run - m_new);
        const float p00 = exp2f(fmaf(s[0][0], kScaleLog2, -m_new));
        const float p01 = exp2f(fmaf(s[0][1], kScaleLog2, -m_new));
        const float p10 = exp2f(fmaf(s[1][0], kScaleLog2, -m_new));
        const float p11 = exp2f(fmaf(s[1][1], kScaleLog2, -m_new));
        m_run = m_new;
        l_run = l_run * alpha + ((p00 + p01) + (p10 + p11));
#pragma unroll
        for (int j = 0; j < 16; ++j) { o[j][0] *= alpha; o[j][1] *= alpha; }
        const uint32_t pa0 = pack_bf16(p00, p01), pa2 = pack_bf16(p10, p11);

        mbar_wait(barFull + sV * 8, (iV / kSlots) & 1);
#pragma unroll
        for (int p = 0; p < 8; ++p) {
            const int chunk = 2 * p + (lane >> 4);
            uint32_t vb[4];
            ldsm_x4_t(vb, aV + (chunk >> 3) * 16384 + vRow + (((chunk & 7) ^ (lane & 7)) << 4));
            mma_bf16(o[2 * p], pa0, 0u, pa2, 0u, vb[0], vb[1]);
            mma_bf16(o[2 * p + 1], pa0, 0u, pa2, 0u, vb[2], vb[3]);
        }
        __syncwarp();
        if (lane == 0) mbar_arrive(barEmpty + sV * 8);
    }

    DBG_T(4);
    l_run += __shfl_xor_sync(0xffffffffu, l_run, 1);
    l_run += __shfl_xor_sync(0xffffffffu, l_run, 2);
    if (g < 4) {
        float* dst = sWO + (warp * 4 + g) * kDh + 2 * t;
#pragma unroll
        for (int j = 0; j < 16; ++j) *reinterpret_cast<float2*>(dst + 8 * j) = make_float2(o[j][0], o[j][1]);
        if (t == 0) { sML[warp * 8 + g] = m_run; sML[warp * 8 + 4 + g] = l_run; }
    }
    tail_phase(tid, smem, cta, epoch, out);
    DBG_T(9);
}

typedef CUresult (*EncodeTiledFn)(CUtensorMap*, CUtensorMapDataType, cuuint32_t, void*, const cuuint64_t*,
                                  const cuuint64_t*, const cuuint32_t*, const cuuint32_t*, CUtensorMapInterleave,
                                  CUtensorMapSwizzle, CUtensorMapL2promotion, CUtensorMapFloatOOBfill);

bool encode_2d(EncodeTiledFn fn, CUtensorMap* tm, const void* base, uint64_t cols, uint64_t rows, uint64_t pitch_bytes,
               uint32_t box_cols, uint32_t box_rows, CUtensorMapSwizzle sw, CUtensorMapL2promotion promo) {
    cuuint64_t dims[2] = {cols, rows};
    cuuint64_t strides[1] = {pitch_bytes};
    cuuint32_t box[2] = {box_cols, box_rows};
    cuuint32_t estr[2] = {1, 1};
    return fn(tm, CU_TENSOR_MAP_DATA_TYPE_BFLOAT16, 2, const_cast<void*>(base), dims, strides, box, estr,
              CU_TENSOR_MAP_INTERLEAVE_NONE, sw, promo, CU_TENSOR_MAP_FLOAT_OOB_FILL_NONE) == CUDA_SUCCESS;
}

}

extern "C" void kernel_launch(void* const* d_in, const int* in_sizes, int n_in, void* d_out, int out_size) {
    (void)in_sizes; (void)n_in; (void)out_size;
    const __nv_bfloat16* x = (const __nv_bfloat16*)d_in[0];
    const void* kc = d_in[1];
    const void* vc = d_in[2];
    const void* wq = d_in[3];
    const void* wo = d_in[4];

    void* fnp = nullptr;
    cudaDriverEntryPointQueryResult qres;
    if (cudaGetDriverEntryPoint("cuTensorMapEncodeTiled", &fnp, cudaEnableDefault, &qres) != cudaSuccess || !fnp) return;
    EncodeTiledFn fn = (EncodeTiledFn)fnp;

    CUtensorMap tmK, tmV, tmWq, tmWo;
    const uint64_t rows = (uint64_t)kB * kHkv * kSk;
    if (!encode_2d(fn, &tmK, kc, kDh, rows, kDh * 2, 64, kTileKeys, CU_TENSOR_MAP_SWIZZLE_128B, CU_TENSOR_MAP_L2_PROMOTION_L2_256B)) return;
    if (!encode_2d(fn, &tmV, vc, kDh, rows, kDh * 2, 64, kTileKeys, CU_TENSOR_MAP_SWIZZLE_128B, CU_TENSOR_MAP_L2_PROMOTION_L2_256B)) return;
    if (!encode_2d(fn, &tmWq, wq, kHqDh, kD, kHqDh * 2, kColsPerCta, 256, CU_TENSOR_MAP_SWIZZLE_64B, CU_TENSOR_MAP_L2_PROMOTION_L2_128B)) return;
    if (!encode_2d(fn, &tmWo, wo, kD, kHqDh, kD * 2, kColsPerCta, 256, CU_TENSOR_MAP_SWIZZLE_64B, CU_TENSOR_MAP_L2_PROMOTION_L2_128B)) return;

    cudaFuncSetAttribute(gqa_decode_fused, cudaFuncAttributeMaxDynamicSharedMemorySize, kSmemBytes);
    gqa_decode_fused<<<kCTAs, kThreads, kSmemBytes>>>(tmK, tmV, tmWq, tmWo, x, (__nv_bfloat16*)d_out);
}
```
